```python
import torch

def _softmax(x, axis=-1):
    return torch.softmax(x, dim=axis)
def _gelu(x):
    return torch.nn.functional.gelu(x, approximate="tanh")
def _silu(x):
    return torch.nn.functional.silu(x)
def _sigmoid(x):
    return torch.sigmoid(x)
def _layernorm(x, axis=-1, eps=1e-5):
    m = x.mean(dim=axis, keepdim=True)
    v = x.var(dim=axis, keepdim=True, unbiased=False)
    return (x - m) / torch.sqrt(v + eps)
def _scatter_add(tgt, idx, src, axis=0):
    return tgt.clone().index_add_(axis, idx, src)
def _segment_sum(src, seg, n):
    out = torch.zeros((n,) + src.shape[1:], dtype=src.dtype)
    return out.index_add_(0, seg, src)
def _pad(x, pw):
    flat = tuple(v for pair in reversed(pw) for v in pair)
    return torch.nn.functional.pad(x, flat)

kernel_name = 'parallel_sum__compressed_kv_cla__mixer_token_mlp__prompt'

def setup_inputs():

    _w = (lambda a: (lambda t: t.to(torch.bfloat16) if t.is_floating_point() else t)(torch.as_tensor(a)))
    def _A_setup():
        B, H, Sq, Sk, D, M = 1, 32, 2048, 2048, 128, 640
        Dc = 4 * D
        return {
            "x": _w((lambda *s: torch.randn(*s, dtype=torch.bfloat16) * 0.05)(B, Sq, M)),
            "c_kv": _w((lambda *s: torch.randn(*s, dtype=torch.bfloat16) * 0.2)(B, Sk, Dc)),
            "w_q": _w((lambda *s: torch.randn(*s, dtype=torch.bfloat16) * 6.4)(M, H, D) * (M ** -0.5)),
            "w_uk": _w((lambda *s: torch.randn(*s, dtype=torch.bfloat16) * 6.4)(Dc, H, D) * (Dc ** -0.5)),
            "w_uv": _w((lambda *s: torch.randn(*s, dtype=torch.bfloat16) * 0.2)(Dc, H, D) * (Dc ** -0.5)),
            "w_o": _w((lambda *s: torch.randn(*s, dtype=torch.bfloat16) * 0.2)(H, D, M) * ((H * D) ** -0.5)),
        }
    _A_in = _A_setup()

    def _B_setup():
        B, S, D, F = 1, 2048, 640, 1728
        return {
            "x": _w((lambda *s: torch.randn(*s, dtype=torch.bfloat16) * 0.05)(B, S, D)),
            "w1": _w((lambda *s: torch.randn(*s, dtype=torch.bfloat16) * 0.4)(S, F) * (S ** -0.5)),
            "b1": _w((lambda *s: torch.randn(*s, dtype=torch.bfloat16) * 3.2)(F) * 0.02),
            "w2": _w((lambda *s: torch.randn(*s, dtype=torch.bfloat16) * 0.2)(F, S) * (F ** -0.5)),
            "b2": _w((lambda *s: torch.randn(*s, dtype=torch.bfloat16) * 0.8)(S) * 0.02),
        }
    _B_in = _B_setup()

    return {
        "A_x": _A_in["x"],
        "A_c_kv": _A_in["c_kv"],
        "A_w_q": _A_in["w_q"],
        "A_w_uk": _A_in["w_uk"],
        "A_w_uv": _A_in["w_uv"],
        "A_w_o": _A_in["w_o"],
        "B_x": _B_in["x"],
        "B_w1": _B_in["w1"],
        "B_b1": _B_in["b1"],
        "B_w2": _B_in["w2"],
        "B_b2": _B_in["b2"],
    }

def reference(A_x, A_c_kv, A_w_q, A_w_uk, A_w_uv, A_w_o, B_x, B_w1, B_b1, B_w2, B_b2):
    def _A_ref(x, c_kv, w_q, w_uk, w_uv, w_o):
        B, Sq, M = x.shape[0], x.shape[1], x.shape[2]
        Sk = c_kv.shape[1]
        H, D = w_q.shape[1], w_q.shape[2]
        q = torch.einsum("bqm,mhd->bhqd", x, w_q)
        k = torch.einsum("bkc,chd->bhkd", c_kv, w_uk)
        v = torch.einsum("bkc,chd->bhkd", c_kv, w_uv)
        scores = torch.einsum("bhqd,bhkd->bhqk", q, k) * (D ** -0.5)
        off = Sk - Sq
        qi = torch.arange(Sq)[:, None]
        kj = torch.arange(Sk)[None, :]
        cmask = kj <= (qi + off)
        scores = torch.where(cmask[None, None], scores, -1e9)
        p = _softmax(scores, axis=-1)
        ctx = torch.einsum("bhqk,bhkd->bhqd", p, v)
        return torch.einsum("bhqd,hdm->bqm", ctx, w_o)

    def _B_ref(x, w1, b1, w2, b2):
        B, S, D = x.shape
        h = _layernorm(x, axis=-1)
        u = torch.einsum("bsd,sf->bdf", h, w1) + b1
        u = _gelu(u)
        y = torch.einsum("bdf,fs->bds", u, w2) + b2
        return (lambda x, *d: x.permute(*d))(y, 0, 2, 1)

    x = A_x
    xn = _layernorm(x, axis=-1)
    return x + _A_ref(xn, A_c_kv, A_w_q, A_w_uk, A_w_uv, A_w_o) + _B_ref(xn, B_w1, B_b1, B_w2, B_b2)
```

```cpp
#include <cuda_runtime.h>
#include <cuda_bf16.h>
#include <cuda.h>
#include <stdint.h>

#define MK_PREG 40
#define MK_CREG 232
#define MK_THR 1.8446744e19f
namespace mk {

constexpr int S_ = 2048, M_ = 640, DC_ = 512, H_ = 32, D_ = 128, F_ = 1728, HD_ = 4096;
constexpr int NSLOT = 7;
constexpr int SLOT = 32768;
constexpr int QD = 4;
constexpr int NPIECE = 3;
constexpr int NMIXP = 1;

__constant__ uint8_t c_piece_a[NPIECE] = {0, 0, 26};
__constant__ uint8_t c_piece_b[NPIECE] = {14, 26, 32};
constexpr int NTILE_OUT = 40;
constexpr unsigned ITEM_END = 0xFFFFu;
enum { T_KV = 0, T_MIX1 = 1, T_ATT = 2, T_OUT = 3, T_FIN = 4 };

constexpr int SMEM_BYTES = NSLOT * SLOT + 1024 + 512;

__device__ __align__(1024) __nv_bfloat16 g_xn[S_ * M_];
__device__ __align__(1024) __nv_bfloat16 g_h[S_ * M_];
__device__ __align__(1024) __nv_bfloat16 g_kv[S_ * 2 * HD_];
__device__ __align__(1024) __nv_bfloat16 g_ctx[S_ * HD_];
__device__ __align__(1024) __nv_bfloat16 g_u[M_ * F_];
__device__ __align__(1024) float g_part[NTILE_OUT * NPIECE * 32768];

struct Flags {
  unsigned sched[8];
  unsigned exit_cnt;
  unsigned pad0[7];
  unsigned ln[16];
  unsigned kv[16 * 16];
  unsigned u[8];
  unsigned ctx[8 * 32];
  unsigned part[NTILE_OUT];
};
static_assert(sizeof(Flags) % 16 == 0, "flags are cleared with 16-byte stores");
__device__ __align__(128) Flags g_flags;

constexpr int N_ITEMS = 1339;
constexpr int N_PHASES = 1;
[[maybe_unused]] static const int c_phase_begin[N_PHASES + 1] = {0, 1339};
__constant__ uint16_t c_items[N_ITEMS] = {
  0, 256, 16, 272, 32, 288, 48, 304, 64, 320, 80, 336, 96, 352, 112, 368,
  128, 384, 144, 400, 160, 416, 176, 432, 192, 448, 208, 464, 224, 480, 240, 496,
  1, 257, 17, 273, 33, 289, 49, 305, 65, 321, 81, 337, 97, 353, 113, 369,
  129, 385, 145, 401, 161, 417, 177, 433, 193, 449, 209, 465, 225, 481, 241, 497,
  2, 258, 18, 274, 34, 290, 50, 306, 66, 322, 82, 338, 98, 354, 114, 370,
  130, 386, 146, 402, 162, 418, 178, 434, 194, 450, 210, 466, 226, 482, 242, 498,
  3, 259, 19, 275, 35, 291, 51, 307, 67, 323, 83, 339, 99, 355, 115, 371,
  131, 387, 147, 403, 163, 419, 179, 435, 195, 451, 211, 467, 227, 483, 243, 499,
  4, 260, 20, 276, 36, 292, 52, 308, 68, 324, 84, 340, 100, 356, 116, 372,
  132, 388, 148, 404, 164, 420, 180, 436, 196, 452, 212, 468, 228, 484, 244, 500,
  5, 261, 21, 277, 37, 293, 53, 309, 69, 325, 85, 341, 101, 357, 117, 373,
  133, 389, 149, 405, 165, 421, 181, 437, 197, 453, 213, 469, 229, 485, 245, 501,
  6, 262, 22, 278, 38, 294, 54, 310, 70, 326, 86, 342, 8192, 8200, 8208, 8216,
  8224, 8193, 8201, 8209, 8217, 8225, 8194, 8202, 8210, 8218, 8226, 8195, 8203, 8211, 8219, 8227,
  8196, 8204, 8212, 8220, 8228, 8197, 8205, 8213, 8221, 8229, 8198, 8206, 8214, 8222, 8230, 102,
  358, 118, 374, 134, 390, 150, 406, 166, 422, 182, 438, 198, 454, 214, 470, 230,
  486, 246, 502, 7, 263, 23, 279, 39, 16864, 16865, 16832, 16833, 16800, 16801, 16768, 16769,
  16736, 16737, 16704, 16705, 16672, 16673, 16640, 16641, 16608, 16866, 16609, 16576, 16867, 16834, 16577, 16544,
  16835, 16802, 16545, 16512, 16803, 16770, 16513, 16480, 16771, 16738, 16481, 16448, 16739, 16706, 16449, 16416,
  16707, 16674, 16417, 16384, 16675, 16642, 16385, 16643, 16610, 16868, 16611, 16578, 16869, 16836, 16579, 16546,
  16837, 16804, 16547, 16514, 16805, 16772, 16515, 16482, 16773, 16740, 16483, 16450, 16741, 16708, 16451, 16418,
  16709, 16676, 16419, 16386, 16677, 16644, 16387, 16645, 16612, 16870, 16613, 16580, 16871, 16838, 16581, 16548,
  16839, 16806, 16549, 16516, 16807, 16774, 16517, 16484, 16775, 16742, 16485, 16452, 16743, 16710, 16453, 16420,
  16711, 16678, 16421, 16388, 16679, 16646, 16389, 16647, 16614, 16872, 16615, 16582, 16873, 16840, 16583, 16550,
  16841, 16808, 16551, 16518, 16809, 16776, 16519, 16486, 16777, 16744, 16487, 16454, 16745, 16712, 16455, 16422,
  16713, 16680, 16423, 16390, 16681, 16648, 16391, 16649, 16616, 16874, 16617, 16584, 16875, 16842, 16585, 16552,
  16843, 16810, 16553, 16520, 16811, 16778, 16521, 16488, 16779, 16746, 16489, 16456, 16747, 16714, 16457, 16424,
  16715, 16682, 16425, 16392, 295, 55, 311, 16683, 16650, 16393, 71, 327, 87, 343, 16651, 16618,
  103, 359, 16876, 119, 375, 16619, 16586, 135, 391, 16877, 16844, 151, 407, 16587, 16554, 167,
  423, 16845, 16812, 183, 439, 16555, 16522, 199, 455, 16813, 16780, 215, 471, 16523, 16490, 231,
  487, 16781, 16748, 247, 503, 16491, 16458, 16749, 16716, 16459, 16426, 8, 264, 24, 280, 16717,
  16684, 16427, 16394, 40, 296, 56, 312, 16685, 16652, 16395, 72, 328, 88, 344, 16653, 16620,
  104, 360, 16878, 120, 376, 16621, 16588, 136, 392, 16879, 16846, 152, 408, 16589, 16556, 168,
  424, 16847, 16814, 184, 440, 16557, 16524, 200, 456, 16815, 16782, 216, 472, 16525, 16492, 232,
  488, 16783, 16750, 248, 504, 16493, 16460, 16751, 16718, 16461, 16428, 9, 265, 25, 281, 16719,
  16686, 16429, 16396, 41, 297, 57, 313, 16687, 16654, 16397, 73, 329, 89, 345, 16655, 16622,
  105, 361, 16880, 121, 377, 16623, 16590, 137, 393, 16881, 16848, 153, 409, 16591, 16558, 169,
  425, 16849, 16816, 185, 441, 16559, 16526, 201, 457, 16817, 16784, 217, 473, 16527, 16494, 233,
  489, 16785, 16752, 249, 505, 16495, 16462, 16753, 16720, 16463, 16430, 10, 266, 26, 282, 16721,
  16688, 16431, 16398, 42, 298, 58, 314, 16689, 16656, 16399, 74, 330, 90, 346, 16657, 16624,
  106, 362, 16882, 122, 378, 16625, 16592, 138, 394, 154, 410, 16883, 16850, 16593, 16560, 170,
  426, 16851, 16818, 186, 442, 16561, 16528, 202, 458, 16819, 16786, 218, 474, 16529, 16496, 234,
  490, 16787, 16754, 250, 506, 16497, 16464, 16755, 16722, 16465, 16432, 11, 267, 27, 283, 16723,
  16690, 16433, 16400, 43, 299, 59, 315, 16691, 16658, 16401, 75, 331, 91, 347, 16659, 16626,
  107, 363, 16884, 123, 379, 16627, 16594, 139, 395, 16885, 16852, 155, 411, 16595, 16562, 171,
  427, 16853, 16820, 187, 443, 16563, 16530, 203, 459, 16821, 16788, 219, 475, 16531, 16498, 235,
  491, 16789, 16756, 251, 507, 16499, 16466, 16757, 16724, 16467, 16434, 12, 268, 28, 284, 16725,
  16692, 16435, 16402, 44, 300, 60, 316, 16693, 16660, 16403, 76, 332, 92, 348, 16661, 16628,
  108, 364, 13, 269, 16886, 124, 380, 16629, 16596, 29, 285, 140, 396, 45, 301, 16887,
  16854, 156, 412, 16597, 16564, 61, 317, 172, 428, 77, 333, 16855, 16822, 188, 444, 16565,
  16532, 93, 349, 204, 460, 109, 365, 16823, 16790, 220, 476, 16533, 16500, 125, 381, 236,
  492, 141, 397, 16791, 16758, 252, 508, 16501, 16468, 157, 413, 173, 429, 16759, 16726, 16469,
  16436, 189, 445, 205, 461, 16727, 16694, 16437, 16404, 221, 477, 237, 493, 16695, 16662, 16405,
  253, 509, 16663, 16630, 14, 270, 16888, 16631, 16598, 30, 286, 46, 302, 16889, 16856, 16599,
  16566, 62, 318, 15, 271, 78, 334, 16857, 16824, 16567, 31, 287, 16534, 94, 350, 47,
  303, 110, 366, 16825, 16792, 16535, 63, 319, 16502, 16890, 126, 382, 79, 335, 142, 398,
  16793, 16760, 16503, 16891, 95, 351, 16470, 16858, 158, 414, 111, 367, 174, 430, 16761, 16728,
  16471, 16859, 127, 383, 16438, 16826, 190, 446, 143, 399, 206, 462, 16729, 16696, 16439, 16827,
  159, 415, 16406, 16794, 222, 478, 175, 431, 238, 494, 16697, 16664, 16407, 16795, 191, 447,
  16762, 254, 510, 207, 463, 16665, 16632, 16763, 223, 479, 16730, 239, 495, 16633, 16600, 16731,
  255, 511, 16698, 16601, 16568, 16699, 16666, 16569, 16536, 16667, 16634, 24625, 24753, 24881, 25009, 25137,
  24641, 24769, 24897, 25025, 25153, 24657, 24785, 24913, 25041, 25169, 24673, 24801, 24929, 25057, 25185, 24689,
  24817, 24945, 25073, 25201, 16537, 24609, 24737, 24865, 24993, 25121, 16504, 16892, 16635, 16602, 16505, 16893,
  16472, 16860, 16603, 16570, 16894, 16473, 24593, 24721, 24849, 24977, 25105, 16861, 16440, 16828, 16571, 16538,
  16895, 16862, 16441, 16829, 16408, 16796, 16539, 16506, 16863, 16830, 16409, 24577, 24705, 24833, 24961, 25089,
  16797, 16764, 16507, 16474, 16831, 16798, 16765, 16732, 16475, 16442, 16799, 16766, 16733, 16700, 16443, 16410,
  16767, 16734, 16701, 16668, 16411, 16735, 16702, 16669, 16636, 16703, 16670, 16637, 16604, 16671, 16638, 16605,
  16572, 16639, 16606, 16573, 16540, 24576, 24704, 24832, 24960, 25088, 24592, 24720, 24848, 24976, 25104, 24608,
  24736, 24864, 24992, 25120, 24624, 24752, 24880, 25008, 25136, 24640, 24768, 24896, 25024, 25152, 24656, 24784,
  24912, 25040, 25168, 24672, 24800, 24928, 25056, 25184, 24688, 24816, 24944, 25072, 25200, 16607, 16574, 16541,
  16508, 16575, 16542, 16509, 16476, 16543, 16510, 16477, 16444, 16511, 16478, 16445, 16412, 16479, 16446, 16413,
  16447, 16414, 16415, 24658, 24786, 24914, 25042, 25170, 24642, 24770, 24898, 25026, 25154, 24674, 24802, 24930,
  25058, 25186, 24626, 24754, 24882, 25010, 25138, 24610, 24738, 24866, 24994, 25122, 24690, 24818, 24946, 25074,
  25202, 24594, 24722, 24850, 24978, 25106, 24578, 24706, 24834, 24962, 25090, 32788, 32789, 32790, 32791, 32820,
  32821, 32822, 32823, 32852, 32853, 32854, 32855, 32884, 32885, 32886, 32887, 32916, 32917, 32918, 32919, 32784,
  32785, 32786, 32787, 32816, 32817, 32818, 32819, 32848, 32849, 32850, 32851, 32880, 32881, 32882, 32883, 32912,
  32913, 32914, 32915, 32792, 32793, 32794, 32795, 32824, 32825, 32826, 32827, 32856, 32857, 32858, 32859, 32888,
  32889, 32890, 32891, 32920, 32921, 32922, 32923, 32780, 32781, 32782, 32783, 32812, 32813, 32814, 32815, 32844,
  32845, 32846, 32847, 32876, 32877, 32878, 32879, 32908, 32909, 32910, 32911, 32776, 32777, 32778, 32779, 32808,
  32809, 32810, 32811, 32840, 32841, 32842, 32843, 32872, 32873, 32874, 32875, 32904, 32905, 32906, 32907, 32796,
  32797, 32798, 32799, 32828, 32829, 32830, 32831, 32860, 32861, 32862, 32863, 32892, 32893, 32894, 32895, 32924,
  32925, 32926, 32927, 32772, 32773, 32774, 32775, 32804, 32805, 32806, 32807, 32836, 32837, 32838, 32839, 32868,
  32869, 32870, 32871, 32900, 32901, 32902, 32903, 32768, 32769, 32770, 32771, 32800, 32801, 32802, 32803, 32832,
  32833, 32834, 32835, 32864, 32865, 32866, 32867, 32896, 32897, 32898, 32899,
};

#define TRACE2(seq, ev, v)
#define TRACE(seq, ev)
#define TRACEV(seq, ev, v)

struct Params {
  CUtensorMap xn_q, wq, ckv, wuk, wuv, kv_st, kv_ld, ctx_st, ctx_ld, wo, h, w1, u_st, u_ld, w2, x, out;
  const __nv_bfloat16* xptr;
  const __nv_bfloat16* b1;
  const __nv_bfloat16* b2;
  int item_begin, item_end, sched_idx, do_ln, do_reset, zero;
};

__device__ __forceinline__ uint32_t smem_u32(const void* p) { return (uint32_t)__cvta_generic_to_shared(p); }

__device__ unsigned g_abort;
__device__ __forceinline__ bool spin_check(uint32_t& spins) {
  ++spins;
  if ((spins & 255u) == 0u) {
    if (spins > (1u << 21)) *(volatile unsigned*)&g_abort = 1u;
    return *(volatile unsigned*)&g_abort != 0u;
  }
  return false;
}
__device__ __forceinline__ void mbar_init(uint32_t bar, uint32_t count) {
  asm volatile("mbarrier.init.shared::cta.b64 [%0], %1;" ::"r"(bar), "r"(count) : "memory");
}
__device__ __forceinline__ void mbar_arrive(uint32_t bar) {
  asm volatile("mbarrier.arrive.shared::cta.b64 _, [%0];" ::"r"(bar) : "memory");
}
__device__ __forceinline__ void mbar_arrive_n(uint32_t bar, uint32_t n) {
  asm volatile("mbarrier.arrive.shared::cta.b64 _, [%0], %1;" ::"r"(bar), "r"(n) : "memory");
}
__device__ __forceinline__ void mbar_expect_tx(uint32_t bar, uint32_t bytes) {
  asm volatile("mbarrier.arrive.expect_tx.shared::cta.b64 _, [%0], %1;" ::"r"(bar), "r"(bytes) : "memory");
}
__device__ __forceinline__ void mbar_wait(uint32_t bar, uint32_t parity) {
  asm volatile(
      "{\n.reg .pred p;\n.reg .u32 c;\nmov.u32 c, 0;\n"
      "LW:\nmbarrier.try_wait.parity.shared::cta.b64 p, [%0], %1;\n@p bra LD;\n"
      "add.u32 c, c, 1;\nsetp.lt.u32 p, c, 0x400000;\n@p bra LW;\ntrap;\nLD:\n}\n" ::"r"(bar),
      "r"(parity)
      : "memory");
}
__device__ __forceinline__ void tma_load_3d(uint32_t dst, const CUtensorMap* map, uint32_t bar, int c0, int c1, int c2) {
  asm volatile(
      "cp.async.bulk.tensor.3d.shared::cluster.global.mbarrier::complete_tx::bytes [%0], [%1, {%3, %4, %5}], [%2];"
      ::"r"(dst), "l"(map), "r"(bar), "r"(c0), "r"(c1), "r"(c2)
      : "memory");
}
__device__ __forceinline__ void tma_store_3d(const CUtensorMap* map, uint32_t src, int c0, int c1, int c2) {
  asm volatile("cp.async.bulk.tensor.3d.global.shared::cta.bulk_group [%0, {%2, %3, %4}], [%1];" ::"l"(map), "r"(src),
               "r"(c0), "r"(c1), "r"(c2)
               : "memory");
}
__device__ __forceinline__ void bulk_load(uint32_t dst, const void* src, uint32_t bytes, uint32_t bar) {
  asm volatile("cp.async.bulk.shared::cluster.global.mbarrier::complete_tx::bytes [%0], [%1], %2, [%3];" ::"r"(dst),
               "l"(src), "r"(bytes), "r"(bar)
               : "memory");
}
__device__ __forceinline__ void bulk_store(void* dst, uint32_t src, uint32_t bytes) {
  asm volatile("cp.async.bulk.global.shared::cta.bulk_group [%0], [%1], %2;" ::"l"(dst), "r"(src), "r"(bytes)
               : "memory");
}
__device__ __forceinline__ void bulk_commit() { asm volatile("cp.async.bulk.commit_group;" ::: "memory"); }
__device__ __forceinline__ void bulk_wait_read0() { asm volatile("cp.async.bulk.wait_group.read 0;" ::: "memory"); }
__device__ __forceinline__ void bulk_wait0() { asm volatile("cp.async.bulk.wait_group 0;" ::: "memory"); }
__device__ __forceinline__ void fence_proxy_async() { asm volatile("fence.proxy.async;" ::: "memory"); }
__device__ __forceinline__ void fence_proxy_async_smem() { asm volatile("fence.proxy.async.shared::cta;" ::: "memory"); }
__device__ __forceinline__ unsigned ld_acquire(const unsigned* p) {
  unsigned v;
  asm volatile("ld.acquire.gpu.global.u32 %0, [%1];" : "=r"(v) : "l"(p) : "memory");
  return v;
}
__device__ __forceinline__ uint32_t ldg_u32_v(const void* p) {
  uint32_t v;
  asm volatile("ld.global.nc.b32 %0, [%1];" : "=r"(v) : "l"(p));
  return v;
}
__device__ __forceinline__ uint4 ldg_u128_v(const void* p) {
  uint4 v;
  asm volatile("ld.global.nc.v4.b32 {%0, %1, %2, %3}, [%4];" : "=r"(v.x), "=r"(v.y), "=r"(v.z), "=r"(v.w) : "l"(p));
  return v;
}
__device__ __forceinline__ void red_release_add(unsigned* p, unsigned v) {
  asm volatile("red.release.gpu.global.add.u32 [%0], %1;" ::"l"(p), "r"(v) : "memory");
}
__device__ __forceinline__ void red_relaxed_add(unsigned* p, unsigned v) {
  asm volatile("red.relaxed.gpu.global.add.u32 [%0], %1;" ::"l"(p), "r"(v) : "memory");
}
__device__ __forceinline__ void wgmma_fence() { asm volatile("wgmma.fence.sync.aligned;" ::: "memory"); }
__device__ __forceinline__ void wgmma_commit() { asm volatile("wgmma.commit_group.sync.aligned;" ::: "memory"); }
template <int N>
__device__ __forceinline__ void wgmma_wait() {
  asm volatile("wgmma.wait_group.sync.aligned %0;" ::"n"(N) : "memory");
}
template <int N>
__device__ __forceinline__ void zero_regs(float (&d)[N]) {
#pragma unroll
  for (int i = 0; i < N; i += 2)
    asm volatile("{\n.reg .b64 z;\nmov.b64 z, 0;\nmov.b64 {%0, %1}, z;\n}" : "=f"(d[i]), "=f"(d[i + 1]));
}
template <int N>
__device__ __forceinline__ void fence_regs(float (&d)[N]) {
#pragma unroll
  for (int i = 0; i < N; i++) asm volatile("" : "+f"(d[i])::"memory");
}
__device__ __forceinline__ uint32_t pack_bf16(float lo, float hi) {
  uint32_t r;
  asm("cvt.rn.bf16x2.f32 %0, %1, %2;" : "=r"(r) : "f"(hi), "f"(lo));
  return r;
}
__device__ __forceinline__ float bf_lo(uint32_t v) { return __uint_as_float(v << 16); }
__device__ __forceinline__ float bf_hi(uint32_t v) { return __uint_as_float(v & 0xFFFF0000u); }
__device__ __forceinline__ float bf_round(float x) { return __bfloat162float(__float2bfloat16_rn(x)); }
__device__ __forceinline__ float ex2(float x) {
  float y;
  asm("ex2.approx.ftz.f32 %0, %1;" : "=f"(y) : "f"(x));
  return y;
}
__device__ __forceinline__ void stmatrix_x4(uint32_t addr, uint32_t r0, uint32_t r1, uint32_t r2, uint32_t r3) {
  asm volatile("stmatrix.sync.aligned.m8n8.x4.shared.b16 [%0], {%1, %2, %3, %4};" ::"r"(addr), "r"(r0), "r"(r1),
               "r"(r2), "r"(r3)
               : "memory");
}
__device__ __forceinline__ void stmatrix_x4_t(uint32_t addr, uint32_t r0, uint32_t r1, uint32_t r2, uint32_t r3) {
  asm volatile("stmatrix.sync.aligned.m8n8.x4.trans.shared.b16 [%0], {%1, %2, %3, %4};" ::"r"(addr), "r"(r0), "r"(r1),
               "r"(r2), "r"(r3)
               : "memory");
}
__device__ __forceinline__ void ldmatrix_x4_t(uint32_t addr, uint32_t& r0, uint32_t& r1, uint32_t& r2, uint32_t& r3) {
  asm volatile("ldmatrix.sync.aligned.m8n8.x4.trans.shared.b16 {%0, %1, %2, %3}, [%4];"
               : "=r"(r0), "=r"(r1), "=r"(r2), "=r"(r3)
               : "r"(addr)
               : "memory");
}
__device__ __forceinline__ void ldmatrix_x4(uint32_t addr, uint32_t& r0, uint32_t& r1, uint32_t& r2, uint32_t& r3) {
  asm volatile("ldmatrix.sync.aligned.m8n8.x4.shared.b16 {%0, %1, %2, %3}, [%4];"
               : "=r"(r0), "=r"(r1), "=r"(r2), "=r"(r3)
               : "r"(addr)
               : "memory");
}
__device__ __forceinline__ void mma_16816(float& d0, float& d1, float& d2, float& d3, uint32_t a0, uint32_t a1, uint32_t a2,
                                          uint32_t a3, uint32_t b0, uint32_t b1) {
  asm volatile("mma.sync.aligned.m16n8k16.row.col.f32.bf16.bf16.f32 {%0, %1, %2, %3}, {%4, %5, %6, %7}, {%8, %9}, {%0, %1, %2, %3};"
               : "+f"(d0), "+f"(d1), "+f"(d2), "+f"(d3)
               : "r"(a0), "r"(a1), "r"(a2), "r"(a3), "r"(b0), "r"(b1));
}
__device__ __forceinline__ uint64_t make_desc(uint32_t addr, uint32_t lbo_bytes, uint32_t sbo_bytes) {
  return (uint64_t)((addr & 0x3FFFF) >> 4) | ((uint64_t)(lbo_bytes >> 4) << 16) | ((uint64_t)(sbo_bytes >> 4) << 32) |
         (1ull << 62);
}

template <int TA, int TB>
__device__ __forceinline__ void wgmma_ss_n256(float (&d)[128], uint64_t da, uint64_t db, int scale_d) {
  asm volatile("{\n.reg .pred p;\nsetp.ne.b32 p, %130, 0;\n"
    "wgmma.mma_async.sync.aligned.m64n256k16.f32.bf16.bf16 "
    "{%0, %1, %2, %3, %4, %5, %6, %7, %8, %9, %10, %11, %12, %13, %14, %15, "
    "%16, %17, %18, %19, %20, %21, %22, %23, %24, %25, %26, %27, %28, %29, %30, %31, "
    "%32, %33, %34, %35, %36, %37, %38, %39, %40, %41, %42, %43, %44, %45, %46, %47, "
    "%48, %49, %50, %51, %52, %53, %54, %55, %56, %57, %58, %59, %60, %61, %62, %63, "
    "%64, %65, %66, %67, %68, %69, %70, %71, %72, %73, %74, %75, %76, %77, %78, %79, "
    "%80, %81, %82, %83, %84, %85, %86, %87, %88, %89, %90, %91, %92, %93, %94, %95, "
    "%96, %97, %98, %99, %100, %101, %102, %103, %104, %105, %106, %107, %108, %109, %110, %111, "
    "%112, %113, %114, %115, %116, %117, %118, %119, %120, %121, %122, %123, %124, %125, %126, %127}, "
    "%128, %129, p, 1, 1, %131, %132;\n}\n"
    : "+f"(d[0]), "+f"(d[1]), "+f"(d[2]), "+f"(d[3]), "+f"(d[4]), "+f"(d[5]), "+f"(d[6]), "+f"(d[7]),
      "+f"(d[8]), "+f"(d[9]), "+f"(d[10]), "+f"(d[11]), "+f"(d[12]), "+f"(d[13]), "+f"(d[14]), "+f"(d[15]),
      "+f"(d[16]), "+f"(d[17]), "+f"(d[18]), "+f"(d[19]), "+f"(d[20]), "+f"(d[21]), "+f"(d[22]), "+f"(d[23]),
      "+f"(d[24]), "+f"(d[25]), "+f"(d[26]), "+f"(d[27]), "+f"(d[28]), "+f"(d[29]), "+f"(d[30]), "+f"(d[31]),
      "+f"(d[32]), "+f"(d[33]), "+f"(d[34]), "+f"(d[35]), "+f"(d[36]), "+f"(d[37]), "+f"(d[38]), "+f"(d[39]),
      "+f"(d[40]), "+f"(d[41]), "+f"(d[42]), "+f"(d[43]), "+f"(d[44]), "+f"(d[45]), "+f"(d[46]), "+f"(d[47]),
      "+f"(d[48]), "+f"(d[49]), "+f"(d[50]), "+f"(d[51]), "+f"(d[52]), "+f"(d[53]), "+f"(d[54]), "+f"(d[55]),
      "+f"(d[56]), "+f"(d[57]), "+f"(d[58]), "+f"(d[59]), "+f"(d[60]), "+f"(d[61]), "+f"(d[62]), "+f"(d[63]),
      "+f"(d[64]), "+f"(d[65]), "+f"(d[66]), "+f"(d[67]), "+f"(d[68]), "+f"(d[69]), "+f"(d[70]), "+f"(d[71]),
      "+f"(d[72]), "+f"(d[73]), "+f"(d[74]), "+f"(d[75]), "+f"(d[76]), "+f"(d[77]), "+f"(d[78]), "+f"(d[79]),
      "+f"(d[80]), "+f"(d[81]), "+f"(d[82]), "+f"(d[83]), "+f"(d[84]), "+f"(d[85]), "+f"(d[86]), "+f"(d[87]),
      "+f"(d[88]), "+f"(d[89]), "+f"(d[90]), "+f"(d[91]), "+f"(d[92]), "+f"(d[93]), "+f"(d[94]), "+f"(d[95]),
      "+f"(d[96]), "+f"(d[97]), "+f"(d[98]), "+f"(d[99]), "+f"(d[100]), "+f"(d[101]), "+f"(d[102]), "+f"(d[103]),
      "+f"(d[104]), "+f"(d[105]), "+f"(d[106]), "+f"(d[107]), "+f"(d[108]), "+f"(d[109]), "+f"(d[110]), "+f"(d[111]),
      "+f"(d[112]), "+f"(d[113]), "+f"(d[114]), "+f"(d[115]), "+f"(d[116]), "+f"(d[117]), "+f"(d[118]), "+f"(d[119]),
      "+f"(d[120]), "+f"(d[121]), "+f"(d[122]), "+f"(d[123]), "+f"(d[124]), "+f"(d[125]), "+f"(d[126]), "+f"(d[127])
    : "l"(da), "l"(db), "r"(scale_d), "n"(TA), "n"(TB));
}
template <int TA, int TB>
__device__ __forceinline__ void wgmma_ss_n128(float (&d)[64], uint64_t da, uint64_t db, int scale_d) {
  asm volatile("{\n.reg .pred p;\nsetp.ne.b32 p, %66, 0;\n"
    "wgmma.mma_async.sync.aligned.m64n128k16.f32.bf16.bf16 "
    "{%0, %1, %2, %3, %4, %5, %6, %7, %8, %9, %10, %11, %12, %13, %14, %15, "
    "%16, %17, %18, %19, %20, %21, %22, %23, %24, %25, %26, %27, %28, %29, %30, %31, "
    "%32, %33, %34, %35, %36, %37, %38, %39, %40, %41, %42, %43, %44, %45, %46, %47, "
    "%48, %49, %50, %51, %52, %53, %54, %55, %56, %57, %58, %59, %60, %61, %62, %63}, "
    "%64, %65, p, 1, 1, %67, %68;\n}\n"
    : "+f"(d[0]), "+f"(d[1]), "+f"(d[2]), "+f"(d[3]), "+f"(d[4]), "+f"(d[5]), "+f"(d[6]), "+f"(d[7]),
      "+f"(d[8]), "+f"(d[9]), "+f"(d[10]), "+f"(d[11]), "+f"(d[12]), "+f"(d[13]), "+f"(d[14]), "+f"(d[15]),
      "+f"(d[16]), "+f"(d[17]), "+f"(d[18]), "+f"(d[19]), "+f"(d[20]), "+f"(d[21]), "+f"(d[22]), "+f"(d[23]),
      "+f"(d[24]), "+f"(d[25]), "+f"(d[26]), "+f"(d[27]), "+f"(d[28]), "+f"(d[29]), "+f"(d[30]), "+f"(d[31]),
      "+f"(d[32]), "+f"(d[33]), "+f"(d[34]), "+f"(d[35]), "+f"(d[36]), "+f"(d[37]), "+f"(d[38]), "+f"(d[39]),
      "+f"(d[40]), "+f"(d[41]), "+f"(d[42]), "+f"(d[43]), "+f"(d[44]), "+f"(d[45]), "+f"(d[46]), "+f"(d[47]),
      "+f"(d[48]), "+f"(d[49]), "+f"(d[50]), "+f"(d[51]), "+f"(d[52]), "+f"(d[53]), "+f"(d[54]), "+f"(d[55]),
      "+f"(d[56]), "+f"(d[57]), "+f"(d[58]), "+f"(d[59]), "+f"(d[60]), "+f"(d[61]), "+f"(d[62]), "+f"(d[63])
    : "l"(da), "l"(db), "r"(scale_d), "n"(TA), "n"(TB));
}
template <int TB>
__device__ __forceinline__ void wgmma_rs_n128(float (&d)[64], uint32_t a0, uint32_t a1, uint32_t a2, uint32_t a3, uint64_t db, int scale_d) {
  asm volatile("{\n.reg .pred p;\nsetp.ne.b32 p, %69, 0;\n"
    "wgmma.mma_async.sync.aligned.m64n128k16.f32.bf16.bf16 "
    "{%0, %1, %2, %3, %4, %5, %6, %7, %8, %9, %10, %11, %12, %13, %14, %15, "
    "%16, %17, %18, %19, %20, %21, %22, %23, %24, %25, %26, %27, %28, %29, %30, %31, "
    "%32, %33, %34, %35, %36, %37, %38, %39, %40, %41, %42, %43, %44, %45, %46, %47, "
    "%48, %49, %50, %51, %52, %53, %54, %55, %56, %57, %58, %59, %60, %61, %62, %63}, "
    "{%64, %65, %66, %67}, %68, p, 1, 1, %70;\n}\n"
    : "+f"(d[0]), "+f"(d[1]), "+f"(d[2]), "+f"(d[3]), "+f"(d[4]), "+f"(d[5]), "+f"(d[6]), "+f"(d[7]),
      "+f"(d[8]), "+f"(d[9]), "+f"(d[10]), "+f"(d[11]), "+f"(d[12]), "+f"(d[13]), "+f"(d[14]), "+f"(d[15]),
      "+f"(d[16]), "+f"(d[17]), "+f"(d[18]), "+f"(d[19]), "+f"(d[20]), "+f"(d[21]), "+f"(d[22]), "+f"(d[23]),
      "+f"(d[24]), "+f"(d[25]), "+f"(d[26]), "+f"(d[27]), "+f"(d[28]), "+f"(d[29]), "+f"(d[30]), "+f"(d[31]),
      "+f"(d[32]), "+f"(d[33]), "+f"(d[34]), "+f"(d[35]), "+f"(d[36]), "+f"(d[37]), "+f"(d[38]), "+f"(d[39]),
      "+f"(d[40]), "+f"(d[41]), "+f"(d[42]), "+f"(d[43]), "+f"(d[44]), "+f"(d[45]), "+f"(d[46]), "+f"(d[47]),
      "+f"(d[48]), "+f"(d[49]), "+f"(d[50]), "+f"(d[51]), "+f"(d[52]), "+f"(d[53]), "+f"(d[54]), "+f"(d[55]),
      "+f"(d[56]), "+f"(d[57]), "+f"(d[58]), "+f"(d[59]), "+f"(d[60]), "+f"(d[61]), "+f"(d[62]), "+f"(d[63])
    : "r"(a0), "r"(a1), "r"(a2), "r"(a3), "l"(db), "r"(scale_d), "n"(TB));
}
template <int TA, int TB>
__device__ __forceinline__ void wgmma_ss_n64(float (&d)[32], uint64_t da, uint64_t db, int scale_d) {
  asm volatile("{\n.reg .pred p;\nsetp.ne.b32 p, %34, 0;\n"
    "wgmma.mma_async.sync.aligned.m64n64k16.f32.bf16.bf16 "
    "{%0, %1, %2, %3, %4, %5, %6, %7, %8, %9, %10, %11, %12, %13, %14, %15, "
    "%16, %17, %18, %19, %20, %21, %22, %23, %24, %25, %26, %27, %28, %29, %30, %31}, "
    "%32, %33, p, 1, 1, %35, %36;\n}\n"
    : "+f"(d[0]), "+f"(d[1]), "+f"(d[2]), "+f"(d[3]), "+f"(d[4]), "+f"(d[5]), "+f"(d[6]), "+f"(d[7]),
      "+f"(d[8]), "+f"(d[9]), "+f"(d[10]), "+f"(d[11]), "+f"(d[12]), "+f"(d[13]), "+f"(d[14]), "+f"(d[15]),
      "+f"(d[16]), "+f"(d[17]), "+f"(d[18]), "+f"(d[19]), "+f"(d[20]), "+f"(d[21]), "+f"(d[22]), "+f"(d[23]),
      "+f"(d[24]), "+f"(d[25]), "+f"(d[26]), "+f"(d[27]), "+f"(d[28]), "+f"(d[29]), "+f"(d[30]), "+f"(d[31])
    : "l"(da), "l"(db), "r"(scale_d), "n"(TA), "n"(TB));
}

struct Ctl {
  uint64_t full[NSLOT];
  uint64_t empty[NSLOT];
  uint64_t staged[NSLOT * 2];
  uint64_t qfull[QD];
  uint64_t qempty[QD];
  uint64_t lnbar;
  uint32_t qitem[QD];
  uint32_t done_cnt;
};

#define FWAIT(bar, ph) mbar_wait(bar, ph)
struct Ring {
  uint32_t slot, phase;
  __device__ __forceinline__ void adv() {
    if (++slot == NSLOT) { slot = 0; phase ^= 1; }
  }
  __device__ __forceinline__ void skip(int n) {
    slot += n;
    while (slot >= NSLOT) { slot -= NSLOT; phase ^= 1; }
  }
};

#define FULL_BAR(s) (ctl_addr + (uint32_t)offsetof(Ctl, full) + 8u * (s))
#define EMPTY_BAR(s) (ctl_addr + (uint32_t)offsetof(Ctl, empty) + 8u * (s))
#define STAGED_BAR(s, w) (ctl_addr + (uint32_t)offsetof(Ctl, staged) + 8u * ((s) * 2 + (w)))
#define QFULL_BAR(q) (ctl_addr + (uint32_t)offsetof(Ctl, qfull) + 8u * (q))
#define QEMPTY_BAR(q) (ctl_addr + (uint32_t)offsetof(Ctl, qempty) + 8u * (q))
#define SLOT_ADDR(s) (sbase + (uint32_t)(s) * (uint32_t)SLOT)

__device__ __forceinline__ void release_slot(uint32_t ctl_addr, uint32_t s, int lane) {
  __syncwarp();
  if (lane == 0) mbar_arrive(EMPTY_BAR(s));
}

template <int TA, int TB>
__device__ __forceinline__ void gemm_mainloop(float (&acc)[128], Ring& rg, uint32_t sbase, uint32_t ctl_addr, int cw,
                                              int lane, int nds, bool last_half) {
  uint32_t prevA = 0, prevB = 0;
#pragma unroll 1
  for (int ds = 0; ds < nds; ds++) {
    const uint32_t sA = rg.slot;
    FWAIT(FULL_BAR(sA), rg.phase);
    rg.adv();
    const uint32_t sB0 = rg.slot;
    FWAIT(FULL_BAR(sB0), rg.phase);
    rg.adv();
    const uint64_t dA = TA ? make_desc(SLOT_ADDR(sA) + cw * 16384, 0, 1024) : make_desc(SLOT_ADDR(sA) + cw * 8192, 0, 1024);
    const uint64_t dB0 = TB ? make_desc(SLOT_ADDR(sB0), 8192, 1024) : make_desc(SLOT_ADDR(sB0), 0, 1024);
    wgmma_fence();
#pragma unroll
    for (int k = 0; k < 4; k++) {
      wgmma_ss_n256<TA, TB>(acc, dA + (TA ? k * 128 : k * 2), dB0 + (TB ? k * 128 : k * 2),
                            (k > 0) || (ds > 0));
    }
    wgmma_commit();
    if (ds > 0) {
      wgmma_wait<1>();
      __syncwarp();
      if (lane == 0) { mbar_arrive(EMPTY_BAR(prevA)); mbar_arrive(EMPTY_BAR(prevB)); }
    }
    if (last_half && ds == nds - 1) {
      prevA = sA;
      prevB = sB0;
    } else {
      const uint32_t sB1 = rg.slot;
      FWAIT(FULL_BAR(sB1), rg.phase);
      rg.adv();
      const uint64_t dB1 = TB ? make_desc(SLOT_ADDR(sB1), 8192, 1024) : make_desc(SLOT_ADDR(sB1), 0, 1024);
      const uint64_t dA1 = dA + (TA ? 512 : 1024);
      wgmma_fence();
#pragma unroll
      for (int k = 0; k < 4; k++) {
        wgmma_ss_n256<TA, TB>(acc, dA1 + (TA ? k * 128 : k * 2), dB1 + (TB ? k * 128 : k * 2), 1);
      }
      wgmma_commit();
      wgmma_wait<1>();
      release_slot(ctl_addr, sB0, lane);
      prevA = sA;
      prevB = sB1;
    }
  }
  wgmma_wait<0>();
  fence_regs(acc);
  __syncwarp();
  if (lane == 0) { mbar_arrive(EMPTY_BAR(prevA)); mbar_arrive(EMPTY_BAR(prevB)); }
}

__device__ __forceinline__ float gelu_tanh(float x) {
  const float z = x * fmaf(0.7978845608028654f * 0.044715f, x * x, 0.7978845608028654f);
  float t;
  asm("tanh.approx.f32 %0, %1;" : "=f"(t) : "f"(z));
  const float hx = 0.5f * x;
  return fmaf(hx, t, hx);
}

__device__ __forceinline__ float warp_sum(float v) {
#pragma unroll
  for (int o = 16; o > 0; o >>= 1) v += __shfl_xor_sync(0xffffffffu, v, o);
  return v;
}
__device__ __forceinline__ void ln_inplace(uint2 (&v)[5]) {
  float s = 0.f;
#pragma unroll
  for (int i = 0; i < 5; i++) s += (bf_lo(v[i].x) + bf_hi(v[i].x)) + (bf_lo(v[i].y) + bf_hi(v[i].y));
  const float mean = warp_sum(s) * (1.0f / M_);
  float q = 0.f;
#pragma unroll
  for (int i = 0; i < 5; i++) {
    float a = bf_lo(v[i].x) - mean, b = bf_hi(v[i].x) - mean, c = bf_lo(v[i].y) - mean, d = bf_hi(v[i].y) - mean;
    q += (a * a + b * b) + (c * c + d * d);
  }
  const float var = bf_round(warp_sum(q) * (1.0f / M_));
  const float mb = bf_round(mean);
  const float rs = 1.0f / bf_round(sqrtf(bf_round(var + 1e-5f)));
#pragma unroll
  for (int i = 0; i < 5; i++) {
    const uint32_t t0 = pack_bf16(bf_lo(v[i].x) - mb, bf_hi(v[i].x) - mb);
    const uint32_t t1 = pack_bf16(bf_lo(v[i].y) - mb, bf_hi(v[i].y) - mb);
    v[i].x = pack_bf16(bf_lo(t0) * rs, bf_hi(t0) * rs);
    v[i].y = pack_bf16(bf_lo(t1) * rs, bf_hi(t1) * rs);
  }
}

__global__ void ln_kernel(const __nv_bfloat16* x) {
  const int row = blockIdx.x * 8 + (threadIdx.x >> 5), lane = threadIdx.x & 31;
  uint2 v[5];
  const uint2* src = reinterpret_cast<const uint2*>(x + (size_t)row * M_);
#pragma unroll
  for (int i = 0; i < 5; i++) v[i] = __ldg(src + i * 32 + lane);
  for (int pass = 0; pass < 2; pass++) {
    ln_inplace(v);
    uint2* d = reinterpret_cast<uint2*>((pass ? g_h : g_xn) + (size_t)row * M_);
#pragma unroll
    for (int i = 0; i < 5; i++) d[i * 32 + lane] = v[i];
  }
  if (blockIdx.x == 0 && threadIdx.x < 16) g_flags.ln[threadIdx.x] = 128u;
}

__global__ void __launch_bounds__(384, 1) mega_kernel(const __grid_constant__ Params p) {
  extern __shared__ uint8_t smem_raw[];
  const uint32_t sbase = (smem_u32(smem_raw) + 1023u) & ~1023u;
  const uint32_t ctl_addr = sbase + NSLOT * SLOT;
  Ctl* ctl = reinterpret_cast<Ctl*>(smem_raw + (ctl_addr - smem_u32(smem_raw)));
  const int tid = threadIdx.x;
  const int lane = tid & 31;
  const int warp = tid >> 5;

  const bool ln_active = p.do_ln && blockIdx.x < 128;
  const int ln_row = (blockIdx.x * 8 + (warp - 4)) * 2;
  uint2 v0[5], v1[5];
  if (ln_active && warp >= 4) {
    const uint2* src = reinterpret_cast<const uint2*>(p.xptr + (size_t)ln_row * M_);
#pragma unroll
    for (int i = 0; i < 5; i++) { v0[i] = __ldg(src + i * 32 + lane); v1[i] = __ldg(src + 160 + i * 32 + lane); }
  }
  if (warp == 1 && lane < 17)
    asm volatile("prefetch.tensormap [%0];" ::"l"(reinterpret_cast<const char*>(&p.xn_q) + lane * sizeof(CUtensorMap)) : "memory");
  if (warp == 0) {
    if (lane < NSLOT) {
      mbar_init(FULL_BAR(lane), 1);
      mbar_init(EMPTY_BAR(lane), 8);
      mbar_init(STAGED_BAR(lane, 0), 4);
      mbar_init(STAGED_BAR(lane, 1), 4);
    } else if (lane < NSLOT + QD) {
      mbar_init(QFULL_BAR(lane - NSLOT), 1);
      mbar_init(QEMPTY_BAR(lane - NSLOT), 10);
    } else if (lane == NSLOT + QD) {
      mbar_init(ctl_addr + (uint32_t)offsetof(Ctl, lnbar), 8);
      ctl->done_cnt = 0;
    }
    asm volatile("fence.mbarrier_init.release.cluster;" ::: "memory");
    fence_proxy_async_smem();
  }
  __syncthreads();

#define ROLE_LOCALS()                                                            \
  uint32_t tid_, sraw_ = smem_u32(smem_raw);                                     \
  asm volatile("mov.u32 %0, %%tid.x;" : "=r"(tid_));                             \
  asm volatile("" : "+r"(sraw_));                                                \
  const int tid = (int)tid_, lane = tid & 31;                                    \
  const int warp = __shfl_sync(0xffffffffu, tid >> 5, 0);    \
  const uint32_t sbase = (sraw_ + 1023u) & ~1023u;                               \
  const uint32_t ctl_addr = sbase + NSLOT * SLOT;                                \
  Ctl* ctl = reinterpret_cast<Ctl*>(smem_raw + (ctl_addr - sraw_));              \
  (void)ctl; (void)tid; (void)lane; (void)warp;
  if (warp < 4) {
    asm volatile("setmaxnreg.dec.sync.aligned.u32 %0;" ::"n"(MK_PREG));
    ROLE_LOCALS();
    const bool ln_active = p.do_ln && blockIdx.x < 128;
    if (warp == 0) {
      Ring rg; rg.slot = 0; rg.phase = 0;
      uint32_t qi = 0, qph = 0;
      unsigned* sched = &g_flags.sched[p.sched_idx];
      unsigned nxt = blockIdx.x;
      const unsigned* fptr = nullptr;
      unsigned ftgt = 0;
      uint32_t ready = 0;
#define NEED(j)                                                        \
  {                                                                    \
    uint32_t spins = 0;                                                \
    while (!((ready >> (j)) & 1u)) {                                   \
      const unsigned v = fptr ? ld_acquire(fptr) : 0xffffffffu;        \
      ready = __ballot_sync(0xffffffffu, v >= ftgt);                   \
      if (!((ready >> (j)) & 1u)) {                                    \
        __nanosleep(40);                                               \
        if (spin_check(spins)) break;                                  \
      } else {                                                         \
        fence_proxy_async();                                           \
      }                                                                \
    }                                                                  \
  }
#define ACQ_T0()
#define ACQ_T1()
#define ACQ(bytes)                                            \
  ACQ_T0();                                                   \
  mbar_wait(EMPTY_BAR(rg.slot), rg.phase ^ 1);                \
  ACQ_T1();                                                   \
  if (lane == 0) mbar_expect_tx(FULL_BAR(rg.slot), (bytes));
#define LOAD3(map, off, c1, c2) \
  if (lane == 0) tma_load_3d(SLOT_ADDR(rg.slot) + (off), (map), FULL_BAR(rg.slot), 0, (c1), (c2));
#define STAGE_SLOT()                                 \
  mbar_wait(EMPTY_BAR(rg.slot), rg.phase ^ 1);       \
  if (lane == 0) mbar_arrive(FULL_BAR(rg.slot));     \
  rg.adv();
#define GRAB() if (lane == 0) nxt = atomicAdd(sched, 1u) + gridDim.x;
      auto fetch = [&](uint32_t fq, uint32_t fph) -> unsigned {
        const unsigned idx = __shfl_sync(0xffffffffu, nxt, 0) + (unsigned)p.item_begin;
        const unsigned item = idx < (unsigned)p.item_end ? (unsigned)c_items[idx] : ITEM_END;
        mbar_wait(QEMPTY_BAR(fq), fph ^ 1);
        if (lane == 0) {
          ctl->qitem[fq] = item;
          mbar_arrive(QFULL_BAR(fq));
        }
        const int type = item >> 13;
        fptr = nullptr;
        ftgt = 0;
        if (type == T_MIX1) {
          fptr = lane < 16 ? &g_flags.ln[lane] : nullptr; ftgt = 128;
        } else if (type == T_ATT) {
          const int r = (item >> 5) & 15, h = item & 31;
          fptr = lane <= r ? &g_flags.kv[(h >> 1) * 16 + lane] : (lane == 16 ? &g_flags.ln[r] : nullptr);
          ftgt = lane == 16 ? 128u : 4u;
        } else if (type == T_OUT) {
          const int mt = (item >> 7) & 7, nt = (item >> 4) & 7;
          if ((int)(item & 15) < NMIXP) { fptr = &g_flags.u[mt]; ftgt = 14; }
          else { fptr = &g_flags.ctx[nt * 32 + lane]; ftgt = 4; }
        } else if (type == T_FIN) {
          fptr = &g_flags.part[((item >> 5) & 7) * 8 + ((item >> 2) & 7)]; ftgt = 2 * NPIECE;
        }
        ready = 0xffffffffu;
        if (type != T_KV && item != ITEM_END) {
          const unsigned v = fptr ? ld_acquire(fptr) : 0xffffffffu;
          ready = __ballot_sync(0xffffffffu, v >= ftgt);
          fence_proxy_async();
        }
        return item;
      };
      unsigned item = fetch(0, 0);
      for (;;) {
        TRACEV(tseq, 0, (long long)item);
        TRACE(tseq, 1);
        if (item == ITEM_END) break;
        const int type = item >> 13;
        int nstage;
        if (type == T_ATT) {
          const int r = (item >> 5) & 15, h = item & 31;
          NEED(16);
#pragma unroll 1
          for (int ks = 0; ks < 10; ks++) {
            ACQ(SLOT);
            LOAD3(&p.xn_q, 0, r * 128, ks);
            LOAD3(&p.wq, 16384, ks * 64, h * 2);
            rg.adv();
          }
#pragma unroll 1
          for (int u = 0; u < 2 * r + 2; u++) {
            const bool last = u == 2 * r + 1;
            const bool is_k = (u == 0) || ((u & 1) && !last);
            const int j = is_k ? (u + 1) >> 1 : (last ? r : (u >> 1) - 1);
            NEED(j);
            if (last) { GRAB(); }
            ACQ(SLOT);
            LOAD3(&p.kv_ld, 0, j * 128, (is_k ? 0 : 64) + h * 2);
            rg.adv();
          }
          nstage = 1;
        } else if (type == T_FIN) {
          const int mt = (item >> 5) & 7, nt = (item >> 2) & 7, qn = item & 3;
          const int tile = mt * 8 + nt;
          ACQ(16384);
          LOAD3(&p.x, 0, nt * 256 + qn * 64, mt * 2);
          rg.adv();
          NEED(0);
          GRAB();
#pragma unroll 1
          for (int pc = 0; pc < NPIECE; pc++) {
            ACQ(SLOT);
            if (lane == 0) bulk_load(SLOT_ADDR(rg.slot), g_part + ((size_t)(tile * NPIECE + pc) * 4 + qn) * 8192, SLOT, FULL_BAR(rg.slot));
            rg.adv();
          }
          nstage = 0;
        } else {
          const CUtensorMap *mA, *mB;
          int a1, a2, ad1, ad2, b1, b2, bd1, bd2, k0 = 0, k1, nb_last = 2;
          bool need_ds = false;
          if (type == T_KV) {
            const int mt = (item >> 4) & 15, nt = item & 15;
            mA = &p.ckv; a1 = mt * 128; a2 = 0; ad1 = 0; ad2 = 2;
            mB = ((item >> 8) & 1) ? &p.wuv : &p.wuk; b1 = 0; b2 = nt * 4; bd1 = 64; bd2 = 0;
            k1 = 4; nstage = 2;
          } else if (type == T_MIX1) {
            const int mt = (item >> 3) & 7, nt = item & 7;
            mA = &p.h; a1 = 0; a2 = mt * 2; ad1 = 128; ad2 = 0;
            mB = &p.w1; b1 = 0; b2 = nt * 4; bd1 = 64; bd2 = 0;
            k1 = 16; nstage = 2; need_ds = true;
          } else {
            const int mt = (item >> 7) & 7, nt = (item >> 4) & 7, piece = item & 15;
            k0 = c_piece_a[piece]; k1 = c_piece_b[piece]; nstage = 4;
            if (piece < NMIXP) {
              mA = &p.u_ld; a1 = mt * 128; a2 = 0; ad1 = 0; ad2 = 2;
              mB = &p.w2; b1 = 0; b2 = nt * 4; bd1 = 64; bd2 = 0;
              if (k1 == 14) nb_last = 1;
            } else {
              mA = &p.wo; a1 = 0; a2 = mt * 2; ad1 = 128; ad2 = 0;
              mB = &p.ctx_ld; b1 = nt * 256; b2 = 0; bd1 = 0; bd2 = 1;
              need_ds = true;
            }
          }
#pragma unroll 1
          for (int ds = k0; ds < k1; ds++) {
            NEED(need_ds ? ds : 0);
            if (ds == k1 - 1) { GRAB(); }
            ACQ(SLOT);
            LOAD3(mA, 0, a1 + ds * ad1, a2 + ds * ad2);
            rg.adv();
            const int nb = ds == k1 - 1 ? nb_last : 2;
#pragma unroll 1
            for (int hb = 0; hb < nb; hb++) {
              ACQ(SLOT);
              LOAD3(mB, 0, b1 + (2 * ds + hb) * bd1, b2 + (2 * ds + hb) * bd2);
              rg.adv();
            }
          }
        }
        TRACE(tseq, 2);
        if (++qi == QD) { qi = 0; qph ^= 1; }
        item = fetch(qi, qph);
#pragma unroll 1
        for (int k = 0; k < nstage; k++) { STAGE_SLOT(); }
      }
    } else {
      if (warp == 3 && ln_active) {
        mbar_wait(ctl_addr + (uint32_t)offsetof(Ctl, lnbar), 0);
        if (lane == 0) {
          fence_proxy_async();
          red_release_add(&g_flags.ln[blockIdx.x >> 3], 16u);
        }
      }
      if (warp <= 2) {
        const int cw = warp - 1;
        Ring rg; rg.slot = 0; rg.phase = 0;
        uint32_t qi = 0, qph = 0, stph = 0;
#define ST_BEGIN()                                                   \
  mbar_wait(STAGED_BAR(rg.slot, cw), (stph >> rg.slot) & 1u);        \
  stph ^= 1u << rg.slot;
#define ST_END()                                                     \
  if (lane == 0) {                                                   \
    bulk_commit();                                                   \
    bulk_wait_read0();                                               \
    mbar_arrive_n(EMPTY_BAR(rg.slot), 4);                            \
  }                                                                  \
  __syncwarp();                                                      \
  rg.adv();
        for (;;) {
          mbar_wait(QFULL_BAR(qi), qph);
          const unsigned item = __shfl_sync(0xffffffffu, ctl->qitem[qi], 0);
          if (item == ITEM_END) break;
          const int type = item >> 13;
          unsigned* flag = nullptr;
          const CUtensorMap* map = nullptr;
          float* pdst = nullptr;
          int c1 = 0, c2 = 0, njobs, pre, post = 0;
          uint32_t soff = cw * 16384;
          if (type == T_KV) {
            const int which = (item >> 8) & 1, mt = (item >> 4) & 15, nt = item & 15;
            pre = 12; njobs = 2; map = &p.kv_st; c1 = mt * 128 + cw * 64; c2 = which * 64 + nt * 4;
            flag = &g_flags.kv[nt * 16 + mt];
          } else if (type == T_MIX1) {
            const int mt = (item >> 3) & 7, nt = item & 7;
            pre = 48; njobs = 2; map = &p.u_st; c1 = mt * 128 + cw * 64; c2 = nt * 4;
            flag = &g_flags.u[mt];
          } else if (type == T_ATT) {
            const int r = (item >> 5) & 15, h = item & 31;
            pre = 10 + 2 * (r + 1); njobs = 1; map = &p.ctx_st; c1 = r * 128 + cw * 64; c2 = h * 2;
            flag = &g_flags.ctx[(r >> 1) * 32 + h];
          } else if (type == T_OUT) {
            const int mt = (item >> 7) & 7, nt = (item >> 4) & 7, piece = item & 15;
            const int tile = mt * 8 + nt;
            const int k0 = c_piece_a[piece], k1 = c_piece_b[piece];
            pre = 3 * (k1 - k0) - ((piece < NMIXP && k1 == 14) ? 1 : 0); njobs = 4;
            pdst = g_part + (size_t)(tile * NPIECE + piece) * 32768 + cw * 4096;
            flag = &g_flags.part[tile];
          } else {
            const int mt = (item >> 5) & 7, nt = (item >> 2) & 7, qn = item & 3;
            pre = 0; post = NPIECE; njobs = 1; map = &p.out; c1 = nt * 256 + qn * 64; c2 = mt * 2 + cw; soff = cw * 8192;
          }
          rg.skip(pre);
#pragma unroll 1
          for (int j = 0; j < njobs; j++) {
            ST_BEGIN();
            if (lane == 0) {
              if (map) tma_store_3d(map, SLOT_ADDR(rg.slot) + soff, 0, c1, c2 + 2 * j);
              else bulk_store(pdst + j * 8192, SLOT_ADDR(rg.slot) + soff, 16384);
            }
            ST_END();
          }
          rg.skip(post);
          if (lane == 0) {
            bulk_wait0();
            if (flag) red_relaxed_add(flag, 1u);
            mbar_arrive(QEMPTY_BAR(qi));
          }
          __syncwarp();
          if (++qi == QD) { qi = 0; qph ^= 1; }
        }
      }
    }
    __syncwarp();
    if (p.do_reset) {
      unsigned last = 0;
      if (lane == 0 && atomicAdd(&ctl->done_cnt, 1u) == 3) {
        __threadfence();
        last = atomicAdd(&g_flags.exit_cnt, 1u) == gridDim.x - 1;
      }
      if (__shfl_sync(0xffffffffu, last, 0)) {
        uint4* f = reinterpret_cast<uint4*>(&g_flags);
        for (int i = lane; i < (int)(sizeof(Flags) / 16); i += 32) f[i] = make_uint4(0, 0, 0, 0);
      }
    }
  } else {
    asm volatile("setmaxnreg.inc.sync.aligned.u32 %0;" ::"n"(MK_CREG));
    ROLE_LOCALS();
    const int cw = (warp >> 2) - 1;
    const int ww = warp & 3;
    Ring rg; rg.slot = 0; rg.phase = 0;
    uint32_t qi = 0, qph = 0;
    if (ln_active) {
#pragma unroll 1
      for (int pass = 0; pass < 2; pass++) {
        ln_inplace(v0);
        ln_inplace(v1);
        uint2* d0 = reinterpret_cast<uint2*>((pass ? g_h : g_xn) + (size_t)ln_row * M_);
#pragma unroll
        for (int i = 0; i < 5; i++) { d0[i * 32 + lane] = v0[i]; d0[160 + i * 32 + lane] = v1[i]; }
      }
      __syncwarp();
      if (lane == 0) mbar_arrive(ctl_addr + (uint32_t)offsetof(Ctl, lnbar));
    }
    const int mi = lane >> 3;
    const int st_row = ww * 16 + (mi & 1) * 8 + (lane & 7);
    for (;;) {
      mbar_wait(QFULL_BAR(qi), qph);
      const unsigned item = __shfl_sync(0xffffffffu, ctl->qitem[qi], 0);
      if (item == ITEM_END) break;
      if (warp == 4) TRACE(tseq, 3);
      const int type = item >> 13;
      if (type == T_ATT) {
        const int r = (item >> 5) & 15;
        float s[64], o[64];
        uint32_t q[32], pp[32];
        zero_regs(s);
        zero_regs(o);
        {
          uint32_t prev = 0;
#pragma unroll 1
          for (int ks = 0; ks < 10; ks++) {
            const uint32_t sl = rg.slot;
            FWAIT(FULL_BAR(sl), rg.phase);
            rg.adv();
            const uint64_t dA = make_desc(SLOT_ADDR(sl) + cw * 8192, 0, 1024);
            const uint64_t dB = make_desc(SLOT_ADDR(sl) + 16384, 8192, 1024);
            wgmma_fence();
#pragma unroll
            for (int k = 0; k < 4; k++) wgmma_ss_n128<0, 1>(s, dA + k * 2, dB + k * 128, (k > 0) || (ks > 0));
            wgmma_commit();
            if (ks > 0) {
              wgmma_wait<1>();
              release_slot(ctl_addr, prev, lane);
            }
            prev = sl;
          }
          wgmma_wait<0>();
          fence_regs(s);
          release_slot(ctl_addr, prev, lane);
#pragma unroll
          for (int i = 0; i < 32; i++) q[i] = pack_bf16(s[2 * i], s[2 * i + 1]);
        }
        if (warp == 4) { TRACE(tseq, 4); TRACE2(tseq, 2, rg.wacc); }
        constexpr float CS = 0.08838834764831845f * 1.4426950408889634f;
        float m0 = -INFINITY, m1 = -INFINITY, l0 = 0.f, l1 = 0.f;
        volatile float sc_mem[2];
        uint32_t pv_slot = 0, k_slot = 0;
        bool resc = false;
        {
          const uint32_t sk = rg.slot;
          FWAIT(FULL_BAR(sk), rg.phase);
          rg.adv();
          const uint64_t dK = make_desc(SLOT_ADDR(sk), 0, 1024);
          if (cw == 1) asm volatile("bar.sync 2, 256;" ::: "memory");
          wgmma_fence();
#pragma unroll
          for (int k = 0; k < 8; k++)
            wgmma_rs_n128<0>(s, q[4 * k], q[4 * k + 1], q[4 * k + 2], q[4 * k + 3], dK + (k >> 2) * 1024 + (k & 3) * 2, k > 0);
          wgmma_commit();
          wgmma_wait<0>();
          fence_regs(s);
          k_slot = sk;
        }
#pragma unroll 1
        for (int j = 0;; j++) {
          float a0, a1;
          if (j == r) {
            uint32_t t_ = tid;
            asm volatile("" : "+r"(t_));
            const int row0 = (int)(((t_ >> 5) - 4) * 16 + ((t_ & 31) >> 2)), colb = 2 * (int)(t_ & 3);
#pragma unroll
            for (int i = 0; i < 16; i++) {
              const int c = 8 * i + colb;
              if (c > row0) s[4 * i] = -INFINITY;
              if (c + 1 > row0) s[4 * i + 1] = -INFINITY;
              if (c > row0 + 8) s[4 * i + 2] = -INFINITY;
              if (c + 1 > row0 + 8) s[4 * i + 3] = -INFINITY;
            }
          }
          if (j == 0) {
            float n0 = m0, n1 = m1;
#pragma unroll
            for (int i = 0; i < 16; i++) {
              n0 = fmaxf(n0, fmaxf(s[4 * i], s[4 * i + 1]));
              n1 = fmaxf(n1, fmaxf(s[4 * i + 2], s[4 * i + 3]));
            }
            n0 = fmaxf(n0, __shfl_xor_sync(0xffffffffu, n0, 1));
            n1 = fmaxf(n1, __shfl_xor_sync(0xffffffffu, n1, 1));
            n0 = fmaxf(n0, __shfl_xor_sync(0xffffffffu, n0, 2));
            n1 = fmaxf(n1, __shfl_xor_sync(0xffffffffu, n1, 2));
            m0 = n0;
            m1 = n1;
            if (cw == 0) asm volatile("bar.arrive 2, 256;" ::: "memory");
          }
          {
            const float mc0 = m0 * CS, mc1 = m1 * CS;
            a0 = 0.f;
            a1 = 0.f;
#pragma unroll
            for (int i = 0; i < 16; i++) {
              s[4 * i] = ex2(fmaf(s[4 * i], CS, -mc0));
              s[4 * i + 1] = ex2(fmaf(s[4 * i + 1], CS, -mc0));
              s[4 * i + 2] = ex2(fmaf(s[4 * i + 2], CS, -mc1));
              s[4 * i + 3] = ex2(fmaf(s[4 * i + 3], CS, -mc1));
              a0 += s[4 * i] + s[4 * i + 1];
              a1 += s[4 * i + 2] + s[4 * i + 3];
            }
          }
          resc = __any_sync(0xffffffffu, !(a0 <= MK_THR) || !(a1 <= MK_THR));
          if (__builtin_expect(resc, 0)) {
            uint32_t ln7 = lane & 7, mi4 = lane >> 3;
            asm volatile("" : "+r"(ln7), "+r"(mi4));
            uint32_t kb = SLOT_ADDR(k_slot) + ln7 * 128;
            const uint32_t o0 = (mi4 ^ ln7) << 4, o1 = ((4 + mi4) ^ ln7) << 4;
#pragma unroll
            for (int nb = 0; nb < 16; nb++) {
              s[4 * nb] = 0.f; s[4 * nb + 1] = 0.f; s[4 * nb + 2] = 0.f; s[4 * nb + 3] = 0.f;
#pragma unroll
              for (int kp = 0; kp < 4; kp++) {
                uint32_t b0, b1, b2, b3;
                ldmatrix_x4(kb + nb * 1024 + (kp >> 1) * 16384 + ((kp & 1) ? o1 : o0), b0, b1, b2, b3);
                mma_16816(s[4 * nb], s[4 * nb + 1], s[4 * nb + 2], s[4 * nb + 3], q[8 * kp], q[8 * kp + 1], q[8 * kp + 2], q[8 * kp + 3], b0, b1);
                mma_16816(s[4 * nb], s[4 * nb + 1], s[4 * nb + 2], s[4 * nb + 3], q[8 * kp + 4], q[8 * kp + 5], q[8 * kp + 6], q[8 * kp + 7], b2, b3);
                kb += __float_as_uint(s[4 * nb]) & (uint32_t)p.zero;
              }
            }
            if (j == r) {
            uint32_t t_ = tid;
            asm volatile("" : "+r"(t_));
            const int row0 = (int)(((t_ >> 5) - 4) * 16 + ((t_ & 31) >> 2)), colb = 2 * (int)(t_ & 3);
#pragma unroll
            for (int i = 0; i < 16; i++) {
              const int c = 8 * i + colb;
              if (c > row0) s[4 * i] = -INFINITY;
              if (c + 1 > row0) s[4 * i + 1] = -INFINITY;
              if (c > row0 + 8) s[4 * i + 2] = -INFINITY;
              if (c + 1 > row0 + 8) s[4 * i + 3] = -INFINITY;
            }
            }
            float n0 = m0, n1 = m1;
#pragma unroll
            for (int i = 0; i < 16; i++) {
              n0 = fmaxf(n0, fmaxf(s[4 * i], s[4 * i + 1]));
              n1 = fmaxf(n1, fmaxf(s[4 * i + 2], s[4 * i + 3]));
            }
            n0 = fmaxf(n0, __shfl_xor_sync(0xffffffffu, n0, 1));
            n1 = fmaxf(n1, __shfl_xor_sync(0xffffffffu, n1, 1));
            n0 = fmaxf(n0, __shfl_xor_sync(0xffffffffu, n0, 2));
            n1 = fmaxf(n1, __shfl_xor_sync(0xffffffffu, n1, 2));
            const float sc0 = ex2((m0 - n0) * CS), sc1 = ex2((m1 - n1) * CS);
            sc_mem[0] = sc0;
            sc_mem[1] = sc1;
            m0 = n0;
            m1 = n1;
            l0 *= sc0;
            l1 *= sc1;
          {
            const float mc0 = m0 * CS, mc1 = m1 * CS;
            a0 = 0.f;
            a1 = 0.f;
#pragma unroll
            for (int i = 0; i < 16; i++) {
              s[4 * i] = ex2(fmaf(s[4 * i], CS, -mc0));
              s[4 * i + 1] = ex2(fmaf(s[4 * i + 1], CS, -mc0));
              s[4 * i + 2] = ex2(fmaf(s[4 * i + 2], CS, -mc1));
              s[4 * i + 3] = ex2(fmaf(s[4 * i + 3], CS, -mc1));
              a0 += s[4 * i] + s[4 * i + 1];
              a1 += s[4 * i + 2] + s[4 * i + 3];
            }
          }
          }
          l0 += a0;
          l1 += a1;
          release_slot(ctl_addr, k_slot, lane);
          if (j == r) break;
          const uint32_t sk = rg.slot;
          FWAIT(FULL_BAR(sk), rg.phase);
          rg.adv();
          const uint32_t sv = rg.slot;
          const uint32_t vph = rg.phase;
          rg.adv();
          const uint64_t dK = make_desc(SLOT_ADDR(sk), 0, 1024);
          const uint64_t dV = make_desc(SLOT_ADDR(sv), 16384, 1024);
          wgmma_wait<0>();
          fence_regs(o);
          fence_regs(s);
          if (j > 0) release_slot(ctl_addr, pv_slot, lane);
          pv_slot = sv;
#pragma unroll
          for (int i = 0; i < 32; i++) pp[i] = pack_bf16(s[2 * i], s[2 * i + 1]);
          wgmma_fence();
#pragma unroll
          for (int k = 0; k < 8; k++)
            wgmma_rs_n128<0>(s, q[4 * k], q[4 * k + 1], q[4 * k + 2], q[4 * k + 3], dK + (k >> 2) * 1024 + (k & 3) * 2, k > 0);
          wgmma_commit();
          FWAIT(FULL_BAR(sv), vph);
          if (__builtin_expect(resc, 0)) {
            const float sc0 = sc_mem[0], sc1 = sc_mem[1];
#pragma unroll
            for (int i = 0; i < 16; i++) {
              o[4 * i] *= sc0;
              o[4 * i + 1] *= sc0;
              o[4 * i + 2] *= sc1;
              o[4 * i + 3] *= sc1;
            }
          }
          wgmma_fence();
#pragma unroll
          for (int k = 0; k < 8; k++)
            wgmma_rs_n128<1>(o, pp[4 * k], pp[4 * k + 1], pp[4 * k + 2], pp[4 * k + 3], dV + k * 128, 1);
          wgmma_commit();
          wgmma_wait<1>();
          fence_regs(s);
          k_slot = sk;
        }
        {
          const uint32_t sv = rg.slot;
          FWAIT(FULL_BAR(sv), rg.phase);
          rg.adv();
          const uint64_t dV = make_desc(SLOT_ADDR(sv), 16384, 1024);
          wgmma_wait<0>();
          fence_regs(o);
          fence_regs(s);
          if (r > 0) release_slot(ctl_addr, pv_slot, lane);
#pragma unroll
          for (int i = 0; i < 16; i++) {
            pp[2 * i] = pack_bf16(s[4 * i], s[4 * i + 1]);
            pp[2 * i + 1] = pack_bf16(s[4 * i + 2], s[4 * i + 3]);
          }
          if (__builtin_expect(resc, 0)) {
            const float sc0 = sc_mem[0], sc1 = sc_mem[1];
#pragma unroll
            for (int i = 0; i < 16; i++) {
              o[4 * i] *= sc0;
              o[4 * i + 1] *= sc0;
              o[4 * i + 2] *= sc1;
              o[4 * i + 3] *= sc1;
            }
          }
          wgmma_fence();
#pragma unroll
          for (int k = 0; k < 8; k++)
            wgmma_rs_n128<1>(o, pp[4 * k], pp[4 * k + 1], pp[4 * k + 2], pp[4 * k + 3], dV + k * 128, 1);
          wgmma_commit();
          l0 += __shfl_xor_sync(0xffffffffu, l0, 1);
          l1 += __shfl_xor_sync(0xffffffffu, l1, 1);
          l0 += __shfl_xor_sync(0xffffffffu, l0, 2);
          l1 += __shfl_xor_sync(0xffffffffu, l1, 2);
          const float i0 = 1.0f / l0, i1 = 1.0f / l1;
          wgmma_wait<0>();
          fence_regs(o);
          release_slot(ctl_addr, sv, lane);
          const uint32_t ss = rg.slot;
          FWAIT(FULL_BAR(ss), rg.phase);
          rg.adv();
          const uint32_t base = SLOT_ADDR(ss) + cw * 16384 + st_row * 128;
#pragma unroll
          for (int i = 0; i < 8; i++) {
            const int cb = 2 * i + (mi >> 1);
            const uint32_t addr = base + (i >> 2) * 8192 + ((uint32_t)((cb & 7) ^ (st_row & 7)) << 4);
            stmatrix_x4(addr, pack_bf16(o[8 * i] * i0, o[8 * i + 1] * i0), pack_bf16(o[8 * i + 2] * i1, o[8 * i + 3] * i1),
                        pack_bf16(o[8 * i + 4] * i0, o[8 * i + 5] * i0), pack_bf16(o[8 * i + 6] * i1, o[8 * i + 7] * i1));
          }
          fence_proxy_async_smem();
          __syncwarp();
          if (lane == 0) mbar_arrive(STAGED_BAR(ss, cw));
        }
      } else if (type == T_FIN) {
        const int nt = (item >> 2) & 7, qn = item & 3;
        float a32[32];
        uint32_t bias[8];
#pragma unroll
        for (int i = 0; i < 8; i++) bias[i] = ldg_u32_v(p.b2 + nt * 256 + qn * 64 + 8 * i + 2 * (lane & 3));
#pragma unroll
        for (int i = 0; i < 32; i++) a32[i] = 0.f;
        const uint32_t xs = rg.slot, xph = rg.phase;
        rg.adv();
#pragma unroll 1
        for (int pc = 0; pc < NPIECE; pc++) {
          const uint32_t ss = rg.slot;
          FWAIT(FULL_BAR(ss), rg.phase);
          rg.adv();
          const uint32_t base = SLOT_ADDR(ss) + cw * 16384 + (tid & 127) * 16;
#pragma unroll
          for (int j = 0; j < 8; j++) {
            float v0, v1, v2, v3;
            asm volatile("ld.shared.v4.f32 {%0, %1, %2, %3}, [%4];"
                         : "=f"(v0), "=f"(v1), "=f"(v2), "=f"(v3)
                         : "r"(base + j * 2048)
                         : "memory");
            a32[4 * j] += v0;
            a32[4 * j + 1] += v1;
            a32[4 * j + 2] += v2;
            a32[4 * j + 3] += v3;
          }
          release_slot(ctl_addr, ss, lane);
        }
        if (warp == 4) { TRACE(tseq, 4); TRACE2(tseq, 2, rg.wacc); }
        const uint32_t ss = xs;
        FWAIT(FULL_BAR(ss), xph);
        const uint32_t base = SLOT_ADDR(ss) + cw * 8192;
#pragma unroll
        for (int i = 0; i < 4; i++) {
          const int srow = 16 * i + (mi >> 1) * 8 + (lane & 7);
          const int chunk = 2 * ww + (mi & 1);
          const uint32_t addr = base + srow * 128 + ((uint32_t)(chunk ^ (srow & 7)) << 4);
          uint32_t x0, x1, x2, x3;
          ldmatrix_x4_t(addr, x0, x1, x2, x3);
          const uint32_t ba = bias[2 * i], bb = bias[2 * i + 1];
          const int a = 8 * i;
          const uint32_t y0 = pack_bf16(a32[a] + bf_lo(x0) + bf_lo(ba), a32[a + 1] + bf_hi(x0) + bf_hi(ba));
          const uint32_t y1 = pack_bf16(a32[a + 2] + bf_lo(x1) + bf_lo(ba), a32[a + 3] + bf_hi(x1) + bf_hi(ba));
          const uint32_t y2 = pack_bf16(a32[a + 4] + bf_lo(x2) + bf_lo(bb), a32[a + 5] + bf_hi(x2) + bf_hi(bb));
          const uint32_t y3 = pack_bf16(a32[a + 6] + bf_lo(x3) + bf_lo(bb), a32[a + 7] + bf_hi(x3) + bf_hi(bb));
          stmatrix_x4_t(addr, y0, y1, y2, y3);
        }
        fence_proxy_async_smem();
        __syncwarp();
        if (lane == 0) mbar_arrive(STAGED_BAR(ss, cw));
      } else {
        float acc[128];
        zero_regs(acc);
        uint4 bv0 = make_uint4(0, 0, 0, 0), bv1 = make_uint4(0, 0, 0, 0);
        const int piece = item & 15;
        const int k0 = type == T_OUT ? c_piece_a[piece] : 0, k1 = type == T_OUT ? c_piece_b[piece] : 4;
        if (type == T_MIX1) {
          const int f0 = (item & 7) * 256 + ((lane >> 3) & 1) * 64 + (lane & 7) * 8;
          if (f0 < F_) bv0 = ldg_u128_v(p.b1 + f0);
          if (f0 + 128 < F_) bv1 = ldg_u128_v(p.b1 + f0 + 128);
          gemm_mainloop<1, 1>(acc, rg, sbase, ctl_addr, cw, lane, 16, false);
        } else if (type == T_KV || piece < NMIXP) {
          gemm_mainloop<0, 1>(acc, rg, sbase, ctl_addr, cw, lane, k1 - k0, k1 == 14);
        } else {
          gemm_mainloop<1, 0>(acc, rg, sbase, ctl_addr, cw, lane, k1 - k0, false);
        }
        if (warp == 4) { TRACE(tseq, 4); TRACE2(tseq, 2, rg.wacc); }
        if (type != T_OUT) {
          uint32_t ss2[2];
#pragma unroll
          for (int hf = 0; hf < 2; hf++) {
            const uint32_t ss = rg.slot;
            ss2[hf] = ss;
            FWAIT(FULL_BAR(ss), rg.phase);
            rg.adv();
            const uint32_t base = SLOT_ADDR(ss) + cw * 16384 + st_row * 128;
#pragma unroll
            for (int i = 0; i < 8; i++) {
              const int cb = 2 * i + (mi >> 1);
              const uint32_t addr = base + (i >> 2) * 8192 + ((uint32_t)((cb & 7) ^ (st_row & 7)) << 4);
              const int a = hf * 64 + 8 * i;
              stmatrix_x4(addr, pack_bf16(acc[a], acc[a + 1]), pack_bf16(acc[a + 2], acc[a + 3]),
                          pack_bf16(acc[a + 4], acc[a + 5]), pack_bf16(acc[a + 6], acc[a + 7]));
            }
            if (type == T_KV) {
              fence_proxy_async_smem();
              __syncwarp();
              if (lane == 0) mbar_arrive(STAGED_BAR(ss, cw));
            }
          }
          if (type == T_MIX1) {
            __syncwarp();
            const int unit = lane & 7, chunk = (lane >> 3) & 1;
#pragma unroll 2
            for (int it = 0; it < 16; it++) {
              const uint4 bv = it < 8 ? bv0 : bv1;
              const int row = ww * 16 + (it & 7) * 2 + (lane >> 4);
              const uint32_t ad = SLOT_ADDR(it < 8 ? ss2[0] : ss2[1]) + cw * 16384 + chunk * 8192 + row * 128 + ((uint32_t)(unit ^ (row & 7)) << 4);
              uint32_t w0, w1, w2, w3;
              asm volatile("ld.shared.v4.b32 {%0, %1, %2, %3}, [%4];" : "=r"(w0), "=r"(w1), "=r"(w2), "=r"(w3) : "r"(ad) : "memory");
              w0 = pack_bf16(bf_lo(w0) + bf_lo(bv.x), bf_hi(w0) + bf_hi(bv.x));
              w0 = pack_bf16(gelu_tanh(bf_lo(w0)), gelu_tanh(bf_hi(w0)));
              w1 = pack_bf16(bf_lo(w1) + bf_lo(bv.y), bf_hi(w1) + bf_hi(bv.y));
              w1 = pack_bf16(gelu_tanh(bf_lo(w1)), gelu_tanh(bf_hi(w1)));
              w2 = pack_bf16(bf_lo(w2) + bf_lo(bv.z), bf_hi(w2) + bf_hi(bv.z));
              w2 = pack_bf16(gelu_tanh(bf_lo(w2)), gelu_tanh(bf_hi(w2)));
              w3 = pack_bf16(bf_lo(w3) + bf_lo(bv.w), bf_hi(w3) + bf_hi(bv.w));
              w3 = pack_bf16(gelu_tanh(bf_lo(w3)), gelu_tanh(bf_hi(w3)));
              asm volatile("st.shared.v4.b32 [%0], {%1, %2, %3, %4};" ::"r"(ad), "r"(w0), "r"(w1), "r"(w2), "r"(w3) : "memory");
            }
            fence_proxy_async_smem();
            __syncwarp();
            if (lane == 0) { mbar_arrive(STAGED_BAR(ss2[0], cw)); mbar_arrive(STAGED_BAR(ss2[1], cw)); }
          }
        } else {
#pragma unroll
          for (int qn = 0; qn < 4; qn++) {
            const uint32_t ss = rg.slot;
            FWAIT(FULL_BAR(ss), rg.phase);
            rg.adv();
            const uint32_t base = SLOT_ADDR(ss) + cw * 16384 + (tid & 127) * 16;
#pragma unroll
            for (int j = 0; j < 8; j++) {
              const int a = qn * 32 + 4 * j;
              asm volatile("st.shared.v4.f32 [%0], {%1, %2, %3, %4};" ::"r"(base + j * 2048), "f"(acc[a]), "f"(acc[a + 1]),
                           "f"(acc[a + 2]), "f"(acc[a + 3])
                           : "memory");
            }
            fence_proxy_async_smem();
            __syncwarp();
            if (lane == 0) mbar_arrive(STAGED_BAR(ss, cw));
          }
        }
      }
      __syncwarp();
      if (lane == 0) mbar_arrive(QEMPTY_BAR(qi));
      if (++qi == QD) { qi = 0; qph ^= 1; }
    }
  }
}

typedef CUresult (*EncodeFn)(CUtensorMap*, CUtensorMapDataType, cuuint32_t, void*, const cuuint64_t*, const cuuint64_t*,
                             const cuuint32_t*, const cuuint32_t*, CUtensorMapInterleave, CUtensorMapSwizzle,
                             CUtensorMapL2promotion, CUtensorMapFloatOOBfill);

static void make_map(EncodeFn enc, CUtensorMap* m, const void* ptr, int rows, int cols, int box_rows, int box_chunks) {
  cuuint64_t dims[3] = {64, (cuuint64_t)rows, (cuuint64_t)(cols / 64)};
  cuuint64_t strides[2] = {(cuuint64_t)cols * 2, 128};
  cuuint32_t box[3] = {64, (cuuint32_t)box_rows, (cuuint32_t)box_chunks};
  cuuint32_t es[3] = {1, 1, 1};
  enc(m, CU_TENSOR_MAP_DATA_TYPE_BFLOAT16, 3, const_cast<void*>(ptr), dims, strides, box, es,
      CU_TENSOR_MAP_INTERLEAVE_NONE, CU_TENSOR_MAP_SWIZZLE_128B, CU_TENSOR_MAP_L2_PROMOTION_L2_256B,
      CU_TENSOR_MAP_FLOAT_OOB_FILL_NONE);
}

static int num_sms() {
  int dev = 0, sms = 0;
  cudaGetDevice(&dev);
  cudaDeviceGetAttribute(&sms, cudaDevAttrMultiProcessorCount, dev);
  return sms;
}

static Params make_params(void* const* d_in, void* d_out) {
  void* fn = nullptr;
  cudaDriverEntryPointQueryResult st;
  cudaGetDriverEntryPoint("cuTensorMapEncodeTiled", &fn, cudaEnableDefault, &st);
  EncodeFn enc = (EncodeFn)fn;
  void *xn, *h, *kv, *ctx, *u;
  cudaGetSymbolAddress(&xn, g_xn);
  cudaGetSymbolAddress(&h, g_h);
  cudaGetSymbolAddress(&kv, g_kv);
  cudaGetSymbolAddress(&ctx, g_ctx);
  cudaGetSymbolAddress(&u, g_u);
  Params p;
  make_map(enc, &p.xn_q, xn, S_, M_, 128, 1);
  make_map(enc, &p.wq, d_in[2], M_, HD_, 64, 2);
  make_map(enc, &p.ckv, d_in[1], S_, DC_, 128, 2);
  make_map(enc, &p.wuk, d_in[3], DC_, HD_, 64, 4);
  make_map(enc, &p.wuv, d_in[4], DC_, HD_, 64, 4);
  make_map(enc, &p.kv_st, kv, S_, 2 * HD_, 64, 2);
  make_map(enc, &p.kv_ld, kv, S_, 2 * HD_, 128, 2);
  make_map(enc, &p.ctx_st, ctx, S_, HD_, 64, 2);
  make_map(enc, &p.ctx_ld, ctx, S_, HD_, 256, 1);
  make_map(enc, &p.wo, d_in[5], HD_, M_, 128, 2);
  make_map(enc, &p.h, h, S_, M_, 128, 2);
  make_map(enc, &p.w1, d_in[7], S_, F_, 64, 4);
  make_map(enc, &p.u_st, u, M_, F_, 64, 2);
  make_map(enc, &p.u_ld, u, M_, F_, 128, 2);
  make_map(enc, &p.w2, d_in[9], F_, S_, 64, 4);
  make_map(enc, &p.x, d_in[0], S_, M_, 64, 2);
  make_map(enc, &p.out, d_out, S_, M_, 64, 1);
  p.xptr = (const __nv_bfloat16*)d_in[0];
  p.b1 = (const __nv_bfloat16*)d_in[8];
  p.b2 = (const __nv_bfloat16*)d_in[10];
  p.item_begin = 0;
  p.item_end = N_ITEMS;
  p.sched_idx = 0;
  p.do_ln = 1;
  p.do_reset = 1;
  p.zero = 0;
  return p;
}

}

#define MK_GRID mk::num_sms()
#define MK_LAUNCH(p) mk::mega_kernel<<<MK_GRID, 384, mk::SMEM_BYTES>>>(p)

extern "C" void kernel_launch(void* const* d_in, const int* in_sizes, int n_in, void* d_out, int out_size) {
  using namespace mk;
  (void)in_sizes; (void)n_in; (void)out_size;
  cudaFuncSetAttribute(mega_kernel, cudaFuncAttributeMaxDynamicSharedMemorySize, SMEM_BYTES);
  Params p = make_params(d_in, d_out);
  if (MK_GRID < 128) {
    p.do_ln = 0;
    ln_kernel<<<S_ / 8, 256>>>(p.xptr);
  }
  MK_LAUNCH(p);
}
```
